```python
import torch

def _softmax(x, axis=-1):
    return torch.softmax(x, dim=axis)

def _gelu(x):
    return torch.nn.functional.gelu(x, approximate='tanh')

def _silu(x):
    return torch.nn.functional.silu(x)

def _sigmoid(x):
    return torch.sigmoid(x)

def _layernorm(x, axis=-1, eps=1e-05):
    m = x.mean(dim=axis, keepdim=True)
    v = x.var(dim=axis, keepdim=True, unbiased=False)
    return (x - m) / torch.sqrt(v + eps)

def _scatter_add(tgt, idx, src, axis=0):
    return tgt.clone().index_add_(axis, idx, src)

def _segment_sum(src, seg, n):
    out = torch.zeros((n,) + src.shape[1:], dtype=src.dtype)
    return out.index_add_(0, seg, src)

def _pad(x, pw):
    flat = tuple((v for pair in reversed(pw) for v in pair))
    return torch.nn.functional.pad(x, flat)
kernel_name = 'adaLN_cond__sliding_block_cached__dense_activation_relu__prompt'

def setup_inputs():

    _w = lambda a: (lambda t: t.to(torch.bfloat16) if t.is_floating_point() else t)(torch.as_tensor(a))

    def _A_setup():
        B, Sq, D = (1, 2048, 448)
        Hq, Hkv, Sk, Dh = (16, 8, 2048, 256)
        assert Hq % Hkv == 0, (Hq, Hkv)
        return {'x': _w((lambda *s: torch.randn(*s, dtype=torch.bfloat16) * 0.05)(B, Sq, D)), 'k_cache': _w((lambda *s: torch.randn(*s, dtype=torch.bfloat16) * 3.2)(B, Hkv, Sk, Dh)), 'v_cache': _w((lambda *s: torch.randn(*s, dtype=torch.bfloat16) * 0.4)(B, Hkv, Sk, Dh)), 'wq': _w((lambda *s: torch.randn(*s, dtype=torch.bfloat16) * 3.2)(D, Hq * Dh) * D ** (-0.5)), 'wo': _w((lambda *s: torch.randn(*s, dtype=torch.bfloat16) * 0.4)(Hq * Dh, D) * (Hq * Dh) ** (-0.5))}
    _A_in = _A_setup()

    def _B_setup():
        B, S, D, Dff = (1, 2048, 448, 1792)
        return {'x': _w((lambda *s: torch.randn(*s, dtype=torch.bfloat16) * 0.05)(B, S, D)), 'w1': _w((lambda *s: torch.randn(*s, dtype=torch.bfloat16) * 0.05)(D, Dff)), 'w2': _w((lambda *s: torch.randn(*s, dtype=torch.bfloat16) * 0.05)(Dff, D))}
    _B_in = _B_setup()
    return {'A_x': _A_in['x'], 'A_k_cache': _A_in['k_cache'], 'A_v_cache': _A_in['v_cache'], 'A_wq': _A_in['wq'], 'A_wo': _A_in['wo'], 'B_x': _B_in['x'], 'B_w1': _B_in['w1'], 'B_w2': _B_in['w2'], 'c': _w((lambda *s: torch.randn(*s, dtype=torch.bfloat16) * 0.1)(1, 448) * 8.0), 'w_mod': _w((lambda *s: torch.randn(*s, dtype=torch.bfloat16) * 0.1)(448, 6 * 448) * 448 ** (-0.5) * 8.0)}

def reference(A_x, A_k_cache, A_v_cache, A_wq, A_wo, B_x, B_w1, B_w2, c, w_mod):

    def _A_ref(x, k_cache, v_cache, wq, wo):
        B, Sq, D = x.shape
        Hq, Dh = (16, 256)
        Hkv, Sk = (k_cache.shape[1], k_cache.shape[2])
        W = min(4096, max(256, Sk // 4))
        rep = Hq // Hkv
        q = (lambda x, *d: x.permute(*d))((x @ wq).reshape(B, Sq, Hq, Dh), 0, 2, 1, 3)
        k = (lambda x, n, axis: torch.repeat_interleave(x, n, dim=axis))(k_cache[:, :, Sk - W:, :], rep, axis=1)
        v = (lambda x, n, axis: torch.repeat_interleave(x, n, dim=axis))(v_cache[:, :, Sk - W:, :], rep, axis=1)
        scores = torch.einsum('bhqd,bhkd->bhqk', q, k) * Dh ** (-0.5)
        p = _softmax(scores, axis=-1)
        o = torch.einsum('bhqk,bhkd->bhqd', p, v)
        return (lambda x, *d: x.permute(*d))(o, 0, 2, 1, 3).reshape(B, Sq, Hq * Dh) @ wo

    def _B_ref(x, w1, w2):
        h = torch.einsum('bsd,df->bsf', x, w1)
        zero = torch.zeros_like(h)
        h = torch.maximum(h, zero)
        return torch.einsum('bsf,fd->bsd', h, w2)
    x = A_x
    mod = (_silu(c) @ w_mod).reshape(c.shape[0], 6, 1, -1)
    sa, ca, ga, sb, cb, gb = (mod[:, 0].clone(), mod[:, 1].clone(), mod[:, 2].clone(), mod[:, 3].clone(), mod[:, 4].clone(), mod[:, 5].clone())
    h = _layernorm(x, axis=-1) * (1 + ca) + sa
    x = x + ga * _A_ref(h, A_k_cache, A_v_cache, A_wq, A_wo)
    h = _layernorm(x, axis=-1) * (1 + cb) + sb
    x = x + gb * _B_ref(h, B_w1, B_w2)
    return x
```

```cpp
#include <cuda_runtime.h>
#include <cuda_bf16.h>
#include <cuda.h>
#include <stdint.h>
#include <type_traits>

constexpr int S_LEN = 2048;
constexpr int DM = 448;
constexpr int HQ = 16;
constexpr int HKV = 8;
constexpr int DH = 256;
constexpr int SK = 2048;
constexpr int WIN = 512;
constexpr int DFF = 1792;
constexpr int S_PAD = S_LEN + 5;

#define TS(i)
__device__ __align__(1024) float g_mod[6 * DM];
__device__ __align__(1024) __nv_bfloat16 g_h[S_LEN * DM];
__device__ __align__(1024) __nv_bfloat16 g_part[HQ * S_PAD * DM];
__device__ __align__(1024) __nv_bfloat16 g_part2[7 * S_PAD * DM];
__device__ __align__(1024) __nv_bfloat16 g_h2[S_LEN * DM];
__device__ __align__(1024) __nv_bfloat16 g_x1[S_LEN * DM];

__device__ __forceinline__ uint32_t smem_u32(const void* p) { return (uint32_t)__cvta_generic_to_shared(p); }

__device__ __forceinline__ void mbar_init(uint32_t bar, uint32_t count) {
  asm volatile("mbarrier.init.shared::cta.b64 [%0], %1;" ::"r"(bar), "r"(count) : "memory");
}
__device__ __forceinline__ void mbar_expect_tx(uint32_t bar, uint32_t bytes) {
  asm volatile("mbarrier.arrive.expect_tx.shared::cta.b64 _, [%0], %1;" ::"r"(bar), "r"(bytes) : "memory");
}
__device__ __forceinline__ void mbar_arrive(uint32_t bar) {
  asm volatile("mbarrier.arrive.shared::cta.b64 _, [%0];" ::"r"(bar) : "memory");
}
__device__ __forceinline__ void mbar_wait(uint32_t bar, uint32_t parity) {
  uint32_t done = 0;
  uint32_t tries = 0;
  while (true) {
    asm volatile(
        "{\n.reg .pred p;\n"
        "mbarrier.try_wait.parity.shared::cta.b64 p, [%1], %2;\n"
        "selp.u32 %0, 1, 0, p;\n}\n"
        : "=r"(done)
        : "r"(bar), "r"(parity)
        : "memory");
    if (done) break;
    if (++tries > (1u << 18)) break;
  }
}
__device__ __forceinline__ void tma_load_3d(uint32_t dst, const CUtensorMap* map, uint32_t bar, int c0, int c1, int c2) {
  asm volatile(
      "cp.async.bulk.tensor.3d.shared::cluster.global.mbarrier::complete_tx::bytes [%0], [%1, {%3, %4, %5}], [%2];"
      ::"r"(dst), "l"((uint64_t)map), "r"(bar), "r"(c0), "r"(c1), "r"(c2)
      : "memory");
}
__device__ __forceinline__ void tma_load_3d_mc(uint32_t dst, const CUtensorMap* map, uint32_t bar, int c0, int c1, int c2) {
  asm volatile(
      "cp.async.bulk.tensor.3d.shared::cluster.global.mbarrier::complete_tx::bytes.multicast::cluster [%0], [%1, {%3, %4, %5}], [%2], %6;"
      ::"r"(dst), "l"((uint64_t)map), "r"(bar), "r"(c0), "r"(c1), "r"(c2), "h"((uint16_t)3)
      : "memory");
}
__device__ __forceinline__ void mbar_arrive_remote(uint32_t rbar) {
  asm volatile("mbarrier.arrive.release.cluster.shared::cluster.b64 _, [%0];" ::"r"(rbar) : "memory");
}
__device__ __forceinline__ void cluster_sync_all() {
  asm volatile("barrier.cluster.arrive.release.aligned;" ::: "memory");
  asm volatile("barrier.cluster.wait.acquire.aligned;" ::: "memory");
}
__device__ __forceinline__ void tma_load_2d(uint32_t dst, const CUtensorMap* map, uint32_t bar, int c0, int c1) {
  asm volatile(
      "cp.async.bulk.tensor.2d.shared::cluster.global.mbarrier::complete_tx::bytes [%0], [%1, {%3, %4}], [%2];"
      ::"r"(dst), "l"((uint64_t)map), "r"(bar), "r"(c0), "r"(c1)
      : "memory");
}
__device__ __forceinline__ void prefetch_tmap(const CUtensorMap* map) {
  asm volatile("prefetch.tensormap [%0];" ::"l"((uint64_t)map) : "memory");
}
__device__ __forceinline__ uint64_t make_desc(uint32_t saddr, uint32_t lbo_bytes, uint32_t sbo_bytes) {
  uint64_t d = 0;
  d |= (uint64_t)((saddr & 0x3FFFF) >> 4);
  d |= (uint64_t)((lbo_bytes >> 4) & 0x3FFF) << 16;
  d |= (uint64_t)((sbo_bytes >> 4) & 0x3FFF) << 32;
  d |= (uint64_t)1 << 62;
  return d;
}
__device__ __forceinline__ uint32_t desc_lo(uint32_t saddr, uint32_t lbo_bytes) {
  return ((saddr & 0x3FFFF) >> 4) | ((lbo_bytes >> 4) << 16);
}
template <int I> struct IC { static constexpr int value = I; };
template <int I, int N, typename F>
__device__ __forceinline__ void static_for(F&& f) {
  if constexpr (I < N) { f(IC<I>{}); static_for<I + 1, N>(f); }
}
__device__ __forceinline__ void wg_fence() { asm volatile("wgmma.fence.sync.aligned;" ::: "memory"); }
__device__ __forceinline__ void wg_commit() { asm volatile("wgmma.commit_group.sync.aligned;" ::: "memory"); }
template <int N>
__device__ __forceinline__ void wg_wait() { asm volatile("wgmma.wait_group.sync.aligned %0;" ::"n"(N) : "memory"); }
__device__ __forceinline__ void fence_async_smem() { asm volatile("fence.proxy.async.shared::cta;" ::: "memory"); }
__device__ __forceinline__ void named_bar(int id, int nthreads) {
  asm volatile("bar.sync %0, %1;" ::"r"(id), "r"(nthreads) : "memory");
}
__device__ __forceinline__ void named_arrive(int id, int nthreads) {
  asm volatile("bar.arrive %0, %1;" ::"r"(id), "r"(nthreads) : "memory");
}
__device__ __forceinline__ uint32_t pack_bf16(float lo, float hi) {
  uint32_t r;
  asm("cvt.rn.bf16x2.f32 %0, %1, %2;" : "=r"(r) : "f"(hi), "f"(lo));
  return r;
}
__device__ __forceinline__ float ex2(float x) {
  float y;
  asm("ex2.approx.ftz.f32 %0, %1;" : "=f"(y) : "f"(x));
  return y;
}
__device__ __forceinline__ void red_add_v2(float* p, float a, float b) {
  asm volatile("red.global.add.v2.f32 [%0], {%1, %2};" ::"l"(p), "f"(a), "f"(b) : "memory");
}
template <int R>
__device__ __forceinline__ void reg_alloc() { asm volatile("setmaxnreg.inc.sync.aligned.u32 %0;" ::"n"(R)); }
template <int R>
__device__ __forceinline__ void reg_dealloc() { asm volatile("setmaxnreg.dec.sync.aligned.u32 %0;" ::"n"(R)); }

__device__ __forceinline__ void tma_reduce_add_2d(const CUtensorMap* map, uint32_t src, int c0, int c1) {
  asm volatile("cp.reduce.async.bulk.tensor.2d.global.shared::cta.add.tile.bulk_group [%0, {%2, %3}], [%1];"
               ::"l"((uint64_t)map), "r"(src), "r"(c0), "r"(c1) : "memory");
}
__device__ __forceinline__ void tma_store_2d(const CUtensorMap* map, uint32_t src, int c0, int c1) {
  asm volatile("cp.async.bulk.tensor.2d.global.shared::cta.tile.bulk_group [%0, {%2, %3}], [%1];"
               ::"l"((uint64_t)map), "r"(src), "r"(c0), "r"(c1) : "memory");
}
__device__ __forceinline__ void bulk_commit() { asm volatile("cp.async.bulk.commit_group;" ::: "memory"); }
__device__ __forceinline__ void bulk_wait_read0() { asm volatile("cp.async.bulk.wait_group.read 0;" ::: "memory"); }
__device__ __forceinline__ void bulk_wait_read1() { asm volatile("cp.async.bulk.wait_group.read 1;" ::: "memory"); }
__device__ __forceinline__ void bulk_wait0() { asm volatile("cp.async.bulk.wait_group 0;" ::: "memory"); }
template <int NB>
__device__ __forceinline__ void flush_boxes(const float* acc, uint32_t stage, const CUtensorMap* map, int col0, int row0,
                                            int r0, int lane, bool elected, int bar_id, bool wait_first) {
  if (wait_first) {
    if (elected) bulk_wait_read1();
    named_bar(bar_id, 128);
  }
  const int cq = (lane & 3) * 2;
#pragma unroll
  for (int j = 0; j < 4 * NB; ++j) {
    uint32_t a = stage + (j >> 2) * 8192 + r0 * 128 + (((((j & 3) << 1) + (cq >> 2)) ^ (r0 & 7)) << 4) + (cq & 3) * 4;
    asm volatile("st.shared.v2.f32 [%0], {%1, %2};" ::"r"(a), "f"(acc[4 * j]), "f"(acc[4 * j + 1]) : "memory");
    asm volatile("st.shared.v2.f32 [%0], {%1, %2};" ::"r"(a + 1024), "f"(acc[4 * j + 2]), "f"(acc[4 * j + 3]) : "memory");
  }
  fence_async_smem();
  named_bar(bar_id, 128);
  if (elected) {
#pragma unroll
    for (int b = 0; b < NB; ++b) tma_store_2d(map, stage + b * 8192, col0 + b * 32, row0);
    bulk_commit();
  }
}

__device__ __forceinline__ void flush_bf16(const float* acc, uint32_t stage, const CUtensorMap* map, int col0, int row0,
                                           int r0, int lane, bool elected, int bar_id, bool wait_first) {
  if (wait_first) {
    if (elected) bulk_wait_read1();
    named_bar(bar_id, 128);
  }
#pragma unroll
  for (int j = 0; j < 8; ++j) {
    uint32_t a = stage + r0 * 128 + ((j ^ (r0 & 7)) << 4) + (lane & 3) * 4;
    asm volatile("st.shared.b32 [%0], %1;" ::"r"(a), "r"(pack_bf16(acc[4 * j], acc[4 * j + 1])) : "memory");
    asm volatile("st.shared.b32 [%0], %1;" ::"r"(a + 1024), "r"(pack_bf16(acc[4 * j + 2], acc[4 * j + 3])) : "memory");
  }
  fence_async_smem();
  named_bar(bar_id, 128);
  if (elected) {
    tma_store_2d(map, stage, col0, row0);
    bulk_commit();
  }
}

template <int AO, int BO>
__device__ __forceinline__ void wgmma_ss_n256_tb(float* d, uint32_t alo, uint32_t blo, int scale_d) {
  asm volatile("{\n.reg .pred p;\n.reg .b32 ta, tb;\n.reg .b64 da, db;\nsetp.ne.b32 p, %130, 0;\n"
    "add.u32 ta, %128, %131;\nadd.u32 tb, %129, %132;\n"
    "mov.b64 da, {ta, 1073741888};\nmov.b64 db, {tb, 1073741888};\n"
    "wgmma.mma_async.sync.aligned.m64n256k16.f32.bf16.bf16 {%0, %1, %2, %3, %4, %5, %6, %7, %8, %9, %10, %11, %12, %13, %14, %15, %16, %17, %18, %19, %20, %21, %22, %23, %24, %25, %26, %27, %28, %29, %30, %31, %32, %33, %34, %35, %36, %37, %38, %39, %40, %41, %42, %43, %44, %45, %46, %47, %48, %49, %50, %51, %52, %53, %54, %55, %56, %57, %58, %59, %60, %61, %62, %63, %64, %65, %66, %67, %68, %69, %70, %71, %72, %73, %74, %75, %76, %77, %78, %79, %80, %81, %82, %83, %84, %85, %86, %87, %88, %89, %90, %91, %92, %93, %94, %95, %96, %97, %98, %99, %100, %101, %102, %103, %104, %105, %106, %107, %108, %109, %110, %111, %112, %113, %114, %115, %116, %117, %118, %119, %120, %121, %122, %123, %124, %125, %126, %127}, da, db, p, 1, 1, 0, 1;\n}\n"
    : "+f"(d[0]), "+f"(d[1]), "+f"(d[2]), "+f"(d[3]), "+f"(d[4]), "+f"(d[5]), "+f"(d[6]), "+f"(d[7]), "+f"(d[8]), "+f"(d[9]), "+f"(d[10]), "+f"(d[11]), "+f"(d[12]), "+f"(d[13]), "+f"(d[14]), "+f"(d[15]), "+f"(d[16]), "+f"(d[17]), "+f"(d[18]), "+f"(d[19]), "+f"(d[20]), "+f"(d[21]), "+f"(d[22]), "+f"(d[23]), "+f"(d[24]), "+f"(d[25]), "+f"(d[26]), "+f"(d[27]), "+f"(d[28]), "+f"(d[29]), "+f"(d[30]), "+f"(d[31]), "+f"(d[32]), "+f"(d[33]), "+f"(d[34]), "+f"(d[35]), "+f"(d[36]), "+f"(d[37]), "+f"(d[38]), "+f"(d[39]), "+f"(d[40]), "+f"(d[41]), "+f"(d[42]), "+f"(d[43]), "+f"(d[44]), "+f"(d[45]), "+f"(d[46]), "+f"(d[47]), "+f"(d[48]), "+f"(d[49]), "+f"(d[50]), "+f"(d[51]), "+f"(d[52]), "+f"(d[53]), "+f"(d[54]), "+f"(d[55]), "+f"(d[56]), "+f"(d[57]), "+f"(d[58]), "+f"(d[59]), "+f"(d[60]), "+f"(d[61]), "+f"(d[62]), "+f"(d[63]), "+f"(d[64]), "+f"(d[65]), "+f"(d[66]), "+f"(d[67]), "+f"(d[68]), "+f"(d[69]), "+f"(d[70]), "+f"(d[71]), "+f"(d[72]), "+f"(d[73]), "+f"(d[74]), "+f"(d[75]), "+f"(d[76]), "+f"(d[77]), "+f"(d[78]), "+f"(d[79]), "+f"(d[80]), "+f"(d[81]), "+f"(d[82]), "+f"(d[83]), "+f"(d[84]), "+f"(d[85]), "+f"(d[86]), "+f"(d[87]), "+f"(d[88]), "+f"(d[89]), "+f"(d[90]), "+f"(d[91]), "+f"(d[92]), "+f"(d[93]), "+f"(d[94]), "+f"(d[95]), "+f"(d[96]), "+f"(d[97]), "+f"(d[98]), "+f"(d[99]), "+f"(d[100]), "+f"(d[101]), "+f"(d[102]), "+f"(d[103]), "+f"(d[104]), "+f"(d[105]), "+f"(d[106]), "+f"(d[107]), "+f"(d[108]), "+f"(d[109]), "+f"(d[110]), "+f"(d[111]), "+f"(d[112]), "+f"(d[113]), "+f"(d[114]), "+f"(d[115]), "+f"(d[116]), "+f"(d[117]), "+f"(d[118]), "+f"(d[119]), "+f"(d[120]), "+f"(d[121]), "+f"(d[122]), "+f"(d[123]), "+f"(d[124]), "+f"(d[125]), "+f"(d[126]), "+f"(d[127])
    : "r"(alo), "r"(blo), "r"(scale_d), "n"(AO >> 4), "n"(BO >> 4));
}
template <int AO, int BO>
__device__ __forceinline__ void wgmma_ss_n64(float* d, uint32_t alo, uint32_t blo, int scale_d) {
  asm volatile("{\n.reg .pred p;\n.reg .b32 ta, tb;\n.reg .b64 da, db;\nsetp.ne.b32 p, %34, 0;\n"
    "add.u32 ta, %32, %35;\nadd.u32 tb, %33, %36;\n"
    "mov.b64 da, {ta, 1073741888};\nmov.b64 db, {tb, 1073741888};\n"
    "wgmma.mma_async.sync.aligned.m64n64k16.f32.bf16.bf16 {%0, %1, %2, %3, %4, %5, %6, %7, %8, %9, %10, %11, %12, %13, %14, %15, %16, %17, %18, %19, %20, %21, %22, %23, %24, %25, %26, %27, %28, %29, %30, %31}, da, db, p, 1, 1, 0, 0;\n}\n"
    : "+f"(d[0]), "+f"(d[1]), "+f"(d[2]), "+f"(d[3]), "+f"(d[4]), "+f"(d[5]), "+f"(d[6]), "+f"(d[7]), "+f"(d[8]), "+f"(d[9]), "+f"(d[10]), "+f"(d[11]), "+f"(d[12]), "+f"(d[13]), "+f"(d[14]), "+f"(d[15]), "+f"(d[16]), "+f"(d[17]), "+f"(d[18]), "+f"(d[19]), "+f"(d[20]), "+f"(d[21]), "+f"(d[22]), "+f"(d[23]), "+f"(d[24]), "+f"(d[25]), "+f"(d[26]), "+f"(d[27]), "+f"(d[28]), "+f"(d[29]), "+f"(d[30]), "+f"(d[31])
    : "r"(alo), "r"(blo), "r"(scale_d), "n"(AO >> 4), "n"(BO >> 4));
}
template <int BO>
__device__ __forceinline__ void wgmma_rs_n256_tb(float* d, const uint32_t* a, uint32_t blo, int scale_d) {
  asm volatile("{\n.reg .pred p;\n.reg .b32 tb;\n.reg .b64 db;\nsetp.ne.b32 p, %133, 0;\n"
    "add.u32 tb, %132, %134;\nmov.b64 db, {tb, 1073741888};\n"
    "wgmma.mma_async.sync.aligned.m64n256k16.f32.bf16.bf16 {%0, %1, %2, %3, %4, %5, %6, %7, %8, %9, %10, %11, %12, %13, %14, %15, %16, %17, %18, %19, %20, %21, %22, %23, %24, %25, %26, %27, %28, %29, %30, %31, %32, %33, %34, %35, %36, %37, %38, %39, %40, %41, %42, %43, %44, %45, %46, %47, %48, %49, %50, %51, %52, %53, %54, %55, %56, %57, %58, %59, %60, %61, %62, %63, %64, %65, %66, %67, %68, %69, %70, %71, %72, %73, %74, %75, %76, %77, %78, %79, %80, %81, %82, %83, %84, %85, %86, %87, %88, %89, %90, %91, %92, %93, %94, %95, %96, %97, %98, %99, %100, %101, %102, %103, %104, %105, %106, %107, %108, %109, %110, %111, %112, %113, %114, %115, %116, %117, %118, %119, %120, %121, %122, %123, %124, %125, %126, %127}, {%128, %129, %130, %131}, db, p, 1, 1, 1;\n}\n"
    : "+f"(d[0]), "+f"(d[1]), "+f"(d[2]), "+f"(d[3]), "+f"(d[4]), "+f"(d[5]), "+f"(d[6]), "+f"(d[7]), "+f"(d[8]), "+f"(d[9]), "+f"(d[10]), "+f"(d[11]), "+f"(d[12]), "+f"(d[13]), "+f"(d[14]), "+f"(d[15]), "+f"(d[16]), "+f"(d[17]), "+f"(d[18]), "+f"(d[19]), "+f"(d[20]), "+f"(d[21]), "+f"(d[22]), "+f"(d[23]), "+f"(d[24]), "+f"(d[25]), "+f"(d[26]), "+f"(d[27]), "+f"(d[28]), "+f"(d[29]), "+f"(d[30]), "+f"(d[31]), "+f"(d[32]), "+f"(d[33]), "+f"(d[34]), "+f"(d[35]), "+f"(d[36]), "+f"(d[37]), "+f"(d[38]), "+f"(d[39]), "+f"(d[40]), "+f"(d[41]), "+f"(d[42]), "+f"(d[43]), "+f"(d[44]), "+f"(d[45]), "+f"(d[46]), "+f"(d[47]), "+f"(d[48]), "+f"(d[49]), "+f"(d[50]), "+f"(d[51]), "+f"(d[52]), "+f"(d[53]), "+f"(d[54]), "+f"(d[55]), "+f"(d[56]), "+f"(d[57]), "+f"(d[58]), "+f"(d[59]), "+f"(d[60]), "+f"(d[61]), "+f"(d[62]), "+f"(d[63]), "+f"(d[64]), "+f"(d[65]), "+f"(d[66]), "+f"(d[67]), "+f"(d[68]), "+f"(d[69]), "+f"(d[70]), "+f"(d[71]), "+f"(d[72]), "+f"(d[73]), "+f"(d[74]), "+f"(d[75]), "+f"(d[76]), "+f"(d[77]), "+f"(d[78]), "+f"(d[79]), "+f"(d[80]), "+f"(d[81]), "+f"(d[82]), "+f"(d[83]), "+f"(d[84]), "+f"(d[85]), "+f"(d[86]), "+f"(d[87]), "+f"(d[88]), "+f"(d[89]), "+f"(d[90]), "+f"(d[91]), "+f"(d[92]), "+f"(d[93]), "+f"(d[94]), "+f"(d[95]), "+f"(d[96]), "+f"(d[97]), "+f"(d[98]), "+f"(d[99]), "+f"(d[100]), "+f"(d[101]), "+f"(d[102]), "+f"(d[103]), "+f"(d[104]), "+f"(d[105]), "+f"(d[106]), "+f"(d[107]), "+f"(d[108]), "+f"(d[109]), "+f"(d[110]), "+f"(d[111]), "+f"(d[112]), "+f"(d[113]), "+f"(d[114]), "+f"(d[115]), "+f"(d[116]), "+f"(d[117]), "+f"(d[118]), "+f"(d[119]), "+f"(d[120]), "+f"(d[121]), "+f"(d[122]), "+f"(d[123]), "+f"(d[124]), "+f"(d[125]), "+f"(d[126]), "+f"(d[127])
    : "r"(a[0]), "r"(a[1]), "r"(a[2]), "r"(a[3]), "r"(blo), "r"(scale_d), "n"(BO >> 4));
}
template <int BO>
__device__ __forceinline__ void wgmma_rs_n128_tb(float* d, const uint32_t* a, uint32_t blo, int scale_d) {
  asm volatile("{\n.reg .pred p;\n.reg .b32 tb;\n.reg .b64 db;\nsetp.ne.b32 p, %69, 0;\n"
    "add.u32 tb, %68, %70;\nmov.b64 db, {tb, 1073741888};\n"
    "wgmma.mma_async.sync.aligned.m64n128k16.f32.bf16.bf16 {%0, %1, %2, %3, %4, %5, %6, %7, %8, %9, %10, %11, %12, %13, %14, %15, %16, %17, %18, %19, %20, %21, %22, %23, %24, %25, %26, %27, %28, %29, %30, %31, %32, %33, %34, %35, %36, %37, %38, %39, %40, %41, %42, %43, %44, %45, %46, %47, %48, %49, %50, %51, %52, %53, %54, %55, %56, %57, %58, %59, %60, %61, %62, %63}, {%64, %65, %66, %67}, db, p, 1, 1, 1;\n}\n"
    : "+f"(d[0]), "+f"(d[1]), "+f"(d[2]), "+f"(d[3]), "+f"(d[4]), "+f"(d[5]), "+f"(d[6]), "+f"(d[7]), "+f"(d[8]), "+f"(d[9]), "+f"(d[10]), "+f"(d[11]), "+f"(d[12]), "+f"(d[13]), "+f"(d[14]), "+f"(d[15]), "+f"(d[16]), "+f"(d[17]), "+f"(d[18]), "+f"(d[19]), "+f"(d[20]), "+f"(d[21]), "+f"(d[22]), "+f"(d[23]), "+f"(d[24]), "+f"(d[25]), "+f"(d[26]), "+f"(d[27]), "+f"(d[28]), "+f"(d[29]), "+f"(d[30]), "+f"(d[31]), "+f"(d[32]), "+f"(d[33]), "+f"(d[34]), "+f"(d[35]), "+f"(d[36]), "+f"(d[37]), "+f"(d[38]), "+f"(d[39]), "+f"(d[40]), "+f"(d[41]), "+f"(d[42]), "+f"(d[43]), "+f"(d[44]), "+f"(d[45]), "+f"(d[46]), "+f"(d[47]), "+f"(d[48]), "+f"(d[49]), "+f"(d[50]), "+f"(d[51]), "+f"(d[52]), "+f"(d[53]), "+f"(d[54]), "+f"(d[55]), "+f"(d[56]), "+f"(d[57]), "+f"(d[58]), "+f"(d[59]), "+f"(d[60]), "+f"(d[61]), "+f"(d[62]), "+f"(d[63])
    : "r"(a[0]), "r"(a[1]), "r"(a[2]), "r"(a[3]), "r"(blo), "r"(scale_d), "n"(BO >> 4));
}
template <int BO>
__device__ __forceinline__ void wgmma_rs_n64_tb(float* d, const uint32_t* a, uint32_t blo, int scale_d) {
  asm volatile("{\n.reg .pred p;\n.reg .b32 tb;\n.reg .b64 db;\nsetp.ne.b32 p, %37, 0;\n"
    "add.u32 tb, %36, %38;\nmov.b64 db, {tb, 1073741888};\n"
    "wgmma.mma_async.sync.aligned.m64n64k16.f32.bf16.bf16 {%0, %1, %2, %3, %4, %5, %6, %7, %8, %9, %10, %11, %12, %13, %14, %15, %16, %17, %18, %19, %20, %21, %22, %23, %24, %25, %26, %27, %28, %29, %30, %31}, {%32, %33, %34, %35}, db, p, 1, 1, 1;\n}\n"
    : "+f"(d[0]), "+f"(d[1]), "+f"(d[2]), "+f"(d[3]), "+f"(d[4]), "+f"(d[5]), "+f"(d[6]), "+f"(d[7]), "+f"(d[8]), "+f"(d[9]), "+f"(d[10]), "+f"(d[11]), "+f"(d[12]), "+f"(d[13]), "+f"(d[14]), "+f"(d[15]), "+f"(d[16]), "+f"(d[17]), "+f"(d[18]), "+f"(d[19]), "+f"(d[20]), "+f"(d[21]), "+f"(d[22]), "+f"(d[23]), "+f"(d[24]), "+f"(d[25]), "+f"(d[26]), "+f"(d[27]), "+f"(d[28]), "+f"(d[29]), "+f"(d[30]), "+f"(d[31])
    : "r"(a[0]), "r"(a[1]), "r"(a[2]), "r"(a[3]), "r"(blo), "r"(scale_d), "n"(BO >> 4));
}

__global__ void __launch_bounds__(256) mod_kernel(const __nv_bfloat16* __restrict__ c, const __nv_bfloat16* __restrict__ w_mod) {
  __shared__ float part[16][33];
  int tid = threadIdx.x;
  int kg = tid >> 4, cp = tid & 15;
  int col = blockIdx.x * 32 + cp * 2;
  __nv_bfloat162 w[28];
#pragma unroll
  for (int i = 0; i < 28; ++i) w[i] = *reinterpret_cast<const __nv_bfloat162*>(w_mod + (size_t)(kg * 28 + i) * (6 * DM) + col);
  float a0 = 0.f, a1 = 0.f;
#pragma unroll
  for (int i = 0; i < 28; ++i) {
    float v = __bfloat162float(c[kg * 28 + i]);
    float sv = __bfloat162float(__float2bfloat16(v / (1.f + __expf(-v))));
    a0 += sv * __bfloat162float(w[i].x);
    a1 += sv * __bfloat162float(w[i].y);
  }
  part[kg][cp * 2] = a0;
  part[kg][cp * 2 + 1] = a1;
  __syncthreads();
  if (tid < 32) {
    float s = 0.f;
#pragma unroll
    for (int i = 0; i < 16; ++i) s += part[i][tid];
    g_mod[blockIdx.x * 32 + tid] = __bfloat162float(__float2bfloat16(s));
  }
}

__global__ void __launch_bounds__(256) ln1_kernel(const __nv_bfloat16* __restrict__ x) {
  int warp = threadIdx.x >> 5, lane = threadIdx.x & 31;
  int row = blockIdx.x * 8 + warp;
  const __nv_bfloat162* xr = reinterpret_cast<const __nv_bfloat162*>(x + (size_t)row * DM);
  float v[14];
  float s = 0.f;
#pragma unroll
  for (int i = 0; i < 7; ++i) {
    __nv_bfloat162 t = xr[lane + 32 * i];
    v[2 * i] = __bfloat162float(t.x);
    v[2 * i + 1] = __bfloat162float(t.y);
    s += v[2 * i] + v[2 * i + 1];
  }
#pragma unroll
  for (int o = 16; o > 0; o >>= 1) s += __shfl_xor_sync(0xffffffffu, s, o);
  float mean = s * (1.f / DM);
  float q = 0.f;
#pragma unroll
  for (int i = 0; i < 14; ++i) { float d = v[i] - mean; q += d * d; }
#pragma unroll
  for (int o = 16; o > 0; o >>= 1) q += __shfl_xor_sync(0xffffffffu, q, o);
  float rstd = rsqrtf(q * (1.f / DM) + 1e-5f);
  __nv_bfloat162* hr = reinterpret_cast<__nv_bfloat162*>(g_h + (size_t)row * DM);
#pragma unroll
  for (int i = 0; i < 7; ++i) {
    int col = 2 * (lane + 32 * i);
    float2 sa = *reinterpret_cast<const float2*>(g_mod + col);
    float2 ca = *reinterpret_cast<const float2*>(g_mod + DM + col);
    float h0 = (v[2 * i] - mean) * rstd * (1.f + ca.x) + sa.x;
    float h1 = (v[2 * i + 1] - mean) * rstd * (1.f + ca.y) + sa.y;
    hr[lane + 32 * i] = __floats2bfloat162_rn(h0, h1);
  }
}

__device__ __forceinline__ void unpack8(uint4 u, float* f) {
  const uint32_t w[4] = {u.x, u.y, u.z, u.w};
#pragma unroll
  for (int i = 0; i < 4; ++i) { f[2 * i] = __uint_as_float(w[i] << 16); f[2 * i + 1] = __uint_as_float(w[i] & 0xffff0000u); }
}
__global__ void __launch_bounds__(128) ln2_kernel(const __nv_bfloat16* __restrict__ x) {
  int warp = threadIdx.x >> 5, lane = threadIdx.x & 31;
  int row = blockIdx.x * 4 + warp;
  const bool act = lane < 28;
  const int colA = act ? lane * 8 : 0;
  float v[16];
#pragma unroll
  for (int i = 0; i < 16; ++i) v[i] = 0.f;
  {
    uint4 p[HQ][2];
    const uint4* pr = reinterpret_cast<const uint4*>(g_part + (size_t)row * DM + colA);
#pragma unroll
    for (int h = 0; h < HQ; ++h) {
      p[h][0] = __ldcg(pr + (size_t)h * (S_PAD * DM / 8));
      p[h][1] = __ldcg(pr + (size_t)h * (S_PAD * DM / 8) + 28);
    }
#pragma unroll
    for (int h = 0; h < HQ; ++h) {
      float f[8];
      unpack8(p[h][0], f);
#pragma unroll
      for (int i = 0; i < 8; ++i) v[i] += f[i];
      unpack8(p[h][1], f);
#pragma unroll
      for (int i = 0; i < 8; ++i) v[8 + i] += f[i];
    }
  }
  float xv[16];
  {
    const uint4* xr = reinterpret_cast<const uint4*>(x + (size_t)row * DM + colA);
    unpack8(xr[0], xv); unpack8(xr[28], xv + 8);
  }
  float s = 0.f;
  uint32_t xo[8];
#pragma unroll
  for (int i = 0; i < 8; ++i) {
    const int col = colA + (i >> 2) * 224 + (i & 3) * 2;
    float2 ga = *reinterpret_cast<const float2*>(g_mod + 2 * DM + col);
    float a0 = __bfloat162float(__float2bfloat16(v[2 * i])), a1 = __bfloat162float(__float2bfloat16(v[2 * i + 1]));
    uint32_t pk = pack_bf16(xv[2 * i] + ga.x * a0, xv[2 * i + 1] + ga.y * a1);
    xo[i] = pk;
    v[2 * i] = __uint_as_float(pk << 16);
    v[2 * i + 1] = __uint_as_float(pk & 0xffff0000u);
    if (act) s += v[2 * i] + v[2 * i + 1];
  }
  if (act) {
    uint4* x1r = reinterpret_cast<uint4*>(g_x1 + (size_t)row * DM + colA);
    x1r[0] = make_uint4(xo[0], xo[1], xo[2], xo[3]);
    x1r[28] = make_uint4(xo[4], xo[5], xo[6], xo[7]);
  }
#pragma unroll
  for (int o = 16; o > 0; o >>= 1) s += __shfl_xor_sync(0xffffffffu, s, o);
  float mean = s * (1.f / DM);
  float q = 0.f;
#pragma unroll
  for (int i = 0; i < 16; ++i) { float d = v[i] - mean; if (act) q += d * d; }
#pragma unroll
  for (int o = 16; o > 0; o >>= 1) q += __shfl_xor_sync(0xffffffffu, q, o);
  float rstd = rsqrtf(q * (1.f / DM) + 1e-5f);
#pragma unroll
  for (int i = 0; i < 8; ++i) {
    const int col = colA + (i >> 2) * 224 + (i & 3) * 2;
    float2 sb = *reinterpret_cast<const float2*>(g_mod + 3 * DM + col);
    float2 cb = *reinterpret_cast<const float2*>(g_mod + 4 * DM + col);
    xo[i] = pack_bf16((v[2 * i] - mean) * rstd * (1.f + cb.x) + sb.x, (v[2 * i + 1] - mean) * rstd * (1.f + cb.y) + sb.y);
  }
  if (act) {
    uint4* hr = reinterpret_cast<uint4*>(g_h2 + (size_t)row * DM + colA);
    hr[0] = make_uint4(xo[0], xo[1], xo[2], xo[3]);
    hr[28] = make_uint4(xo[4], xo[5], xo[6], xo[7]);
  }
}

#define QKN 16
#define PVN 4
#define MCAST 0
constexpr int NST = 5;
constexpr int C_STAGE_BYTES = 32768;
constexpr int C_Q_OFF = 0;
constexpr int C_RING_OFF = 65536;
constexpr int C_BAR_OFF = C_RING_OFF + NST * C_STAGE_BYTES;
constexpr int C_SMEM = C_BAR_OFF + 256;

struct Ctx {
  uint32_t sbase, bar_full, bar_empty, rbar_empty;
  int rank;
};
struct Pos {
  int s; uint32_t ph;
  __device__ __forceinline__ void adv() { if (++s == NST) { s = 0; ph ^= 1; } }
};

__device__ __forceinline__ Ctx make_ctx(uint32_t sbase) {
  Ctx c;
  c.sbase = sbase;
  c.bar_full = sbase + C_BAR_OFF;
  c.bar_empty = c.bar_full + 64;
  c.rank = 0; c.rbar_empty = 0;
  return c;
}
__device__ __forceinline__ void init_bars(const Ctx& c) {
  for (int i = 0; i < NST; ++i) { mbar_init(c.bar_full + 8 * i, 1); mbar_init(c.bar_empty + 8 * i, MCAST ? 16 : 8); }
  asm volatile("fence.mbarrier_init.release.cluster;" ::: "memory");
}
__device__ __forceinline__ void sync_start() {
  __syncthreads();
}
__device__ __forceinline__ void sync_end() {
}
__device__ __forceinline__ void release_slot(const Ctx& c, int s) {
  mbar_arrive(c.bar_empty + 8 * s);
}
__device__ __forceinline__ uint32_t slot_addr(const Ctx& c, int s) { return c.sbase + C_RING_OFF + s * C_STAGE_BYTES; }
__device__ __forceinline__ void prod_ring(const Ctx& c, Pos& p, const CUtensorMap* map, int c1, int c2, int dc1, int dc2) {
  mbar_wait(c.bar_empty + 8 * p.s, p.ph ^ 1);
  mbar_expect_tx(c.bar_full + 8 * p.s, 32768);
  tma_load_3d(slot_addr(c, p.s), map, c.bar_full + 8 * p.s, 0, c1, c2);
  tma_load_3d(slot_addr(c, p.s) + 16384, map, c.bar_full + 8 * p.s, 0, c1 + dc1, c2 + dc2);
  p.adv();
}
__device__ __forceinline__ void prod_gemm1(const Ctx& c, Pos& p, const CUtensorMap* map_a, const CUtensorMap* map_w,
                                           int row0, int group0) {
  for (int kc = 0; kc < 7; ++kc) {
    prod_ring(c, p, map_w, kc * 64, group0, 0, 2);
    mbar_wait(c.bar_empty + 8 * p.s, p.ph ^ 1);
    mbar_expect_tx(c.bar_full + 8 * p.s, 16384);
    tma_load_2d(slot_addr(c, p.s), map_a, c.bar_full + 8 * p.s, kc * 64, row0);
    p.adv();
  }
}
__device__ __forceinline__ void prod_gemm2(const Ctx& c, Pos& p, const CUtensorMap* map, int krow0) {
  for (int ch = 0; ch < 7; ++ch) prod_ring(c, p, map, krow0, ch, 128, 0);
}
__device__ __forceinline__ void cons_gemm1(const Ctx& c, Pos& p, float* acc, int wg, int lane) {
  int pb = 0, pa = 0;
#pragma unroll 1
  for (int kc = 0; kc < 7; ++kc) {
    int sb = p.s;
    mbar_wait(c.bar_full + 8 * p.s, p.ph);
    p.adv();
    int sa = p.s;
    mbar_wait(c.bar_full + 8 * p.s, p.ph);
    p.adv();
    wg_fence();
    {
      uint32_t alo = desc_lo(slot_addr(c, sa) + wg * 8192, 16), blo = desc_lo(slot_addr(c, sb), 8192);
      static_for<0, 4>([&](auto kx) { constexpr int ks = decltype(kx)::value; wgmma_ss_n256_tb<ks * 32, ks * 2048>(acc, alo, blo, (kc | ks) != 0); });
    }
    wg_commit();
    if (kc > 0) {
      wg_wait<1>();
      if (lane == 0) { release_slot(c, pb); release_slot(c, pa); }
    }
    pb = sb; pa = sa;
  }
  wg_wait<0>();
  if (lane == 0) { release_slot(c, pb); release_slot(c, pa); }
}
__device__ __forceinline__ int gemm2_issue(const Ctx& c, Pos& p, float* acc, const uint32_t* oa) {
  int s = p.s;
  mbar_wait(c.bar_full + 8 * p.s, p.ph);
  p.adv();
  wg_fence();
  {
    uint32_t blo = desc_lo(slot_addr(c, s), 16384);
    static_for<0, 16>([&](auto kx) { constexpr int ks = decltype(kx)::value; wgmma_rs_n64_tb<ks * 2048>(acc, oa + 4 * ks, blo, ks != 0); });
  }
  wg_commit();
  return s;
}
__device__ __forceinline__ void cons_gemm2(const Ctx& c, Pos& p, float (&ab)[2][32], const uint32_t* oa, uint32_t stg,
                                           const CUtensorMap* map_out, int orow, int r0, int lane, bool elected, int bar_id) {
  int s0 = gemm2_issue(c, p, ab[0], oa), s1;
#pragma unroll
  for (int q = 0; q < 3; ++q) {
    const int ch = 2 * q;
    s1 = gemm2_issue(c, p, ab[1], oa);
    wg_wait<1>();
    if (lane == 0) release_slot(c, s0);
    flush_bf16(ab[0], stg, map_out, ch * 64, orow, r0, lane, elected, bar_id, q > 0);
    s0 = gemm2_issue(c, p, ab[0], oa);
    wg_wait<1>();
    if (lane == 0) release_slot(c, s1);
    flush_bf16(ab[1], stg + 8192, map_out, ch * 64 + 64, orow, r0, lane, elected, bar_id, q > 0);
  }
  wg_wait<0>();
  if (lane == 0) release_slot(c, s0);
  flush_bf16(ab[0], stg, map_out, 384, orow, r0, lane, elected, bar_id, true);
}

#define CLUSTER_ATTR
__global__ void CLUSTER_ATTR __launch_bounds__(384, 1)
attn_kernel(const __grid_constant__ CUtensorMap map_h, const __grid_constant__ CUtensorMap map_wq,
            const __grid_constant__ CUtensorMap map_k, const __grid_constant__ CUtensorMap map_v,
            const __grid_constant__ CUtensorMap map_wo, const __grid_constant__ CUtensorMap map_acc) {
  extern __shared__ __align__(1024) uint8_t smem[];
  const Ctx c = make_ctx(smem_u32(smem));
  const uint32_t sbase = c.sbase;
  const int tid = threadIdx.x;
  const int wg = __shfl_sync(0xffffffffu, tid >> 7, 0);
  const int qt = blockIdx.x;
  const int g = blockIdx.y;

  if (tid == 0) init_bars(c);
  sync_start();

  if (wg == 2) {
    reg_dealloc<24>();
    if (tid == 256) {
      Pos p{0, 0};
      for (int hh = 0; hh < 2; ++hh) {
        const int head = 2 * g + hh;
        prod_gemm1(c, p, &map_h, &map_wq, qt * 128, head * 4);
        for (int i = 0; i < 16; ++i)
          prod_ring(c, p, (i & 1) ? &map_v : &map_k, g * SK + (SK - WIN) + (i >> 1) * 64, 0, 0, 2);
        prod_gemm2(c, p, &map_wo, head * DH);
      }
    }
    sync_end();
  } else {
    reg_alloc<240>();
    const int warp = (tid >> 5) & 3;
    const int lane = tid & 31;
    const int r0 = warp * 16 + (lane >> 2);
    const uint32_t qbase = sbase + C_Q_OFF + wg * 32768;
    const bool elected = (tid & 127) == 0;
    const int orow = qt * 128 + wg * 64;
    const float sc = 0.0625f * 1.4426950408889634f;
    Pos p{0, 0};
    if (wg == 1) named_arrive(4, 256);
#pragma unroll 1
    for (int hh = 0; hh < 2; ++hh) {
      float acc[128];
#pragma unroll
      for (int i = 0; i < 128; ++i) acc[i] = 0.f;
      TS(hh * 8 + 0);
      cons_gemm1(c, p, acc, wg, lane);
      TS(hh * 8 + 1);
      {
        if (hh > 0) {
          if (elected) bulk_wait_read0();
          named_bar(1 + wg, 128);
        }
#pragma unroll
        for (int j = 0; j < 32; ++j) {
          uint32_t box = qbase + (j >> 3) * 8192;
          uint32_t a0 = box + r0 * 128 + (((j & 7) ^ (r0 & 7)) << 4) + (lane & 3) * 4;
          uint32_t a1 = a0 + 1024;
          uint32_t v0 = pack_bf16(acc[4 * j], acc[4 * j + 1]);
          uint32_t v1 = pack_bf16(acc[4 * j + 2], acc[4 * j + 3]);
          asm volatile("st.shared.b32 [%0], %1;" ::"r"(a0), "r"(v0) : "memory");
          asm volatile("st.shared.b32 [%0], %1;" ::"r"(a1), "r"(v1) : "memory");
        }
        fence_async_smem();
        named_bar(1 + wg, 128);
      }
      TS(hh * 8 + 2);
      float m0 = -INFINITY, m1 = -INFINITY, l0 = 0.f, l1 = 0.f;
#pragma unroll
      for (int i = 0; i < 128; ++i) acc[i] = 0.f;
      float sbuf[2][32];
#pragma unroll
      for (int i = 0; i < 32; ++i) { sbuf[0][i] = 0.f; sbuf[1][i] = 0.f; }
      const uint32_t qlo = desc_lo(qbase, 16);
      int vprev = 0, kcur;
      float* sacc = sbuf[0];
      {
        kcur = p.s;
        mbar_wait(c.bar_full + 8 * p.s, p.ph);
        p.adv();
        named_bar(4 + wg, 256);
        wg_fence();
        uint32_t blo = desc_lo(slot_addr(c, kcur), 16);
        static_for<0, QKN>([&](auto kx) {
          constexpr int ks = decltype(kx)::value;
          wgmma_ss_n64<(ks >> 2) * 8192 + (ks & 3) * 32, (ks >> 2) * 8192 + (ks & 3) * 32>(sacc, qlo, blo, ks != 0);
        });
        wg_commit();
        named_arrive(5 - wg, 256);
      }
#pragma unroll 1
      for (int j = 0; j < 8; ++j) {
        {
          if (j > 0) {
            wg_wait<1>();
            if (lane == 0) release_slot(c, vprev);
          }
          wg_wait<0>();
          if (lane == 0) release_slot(c, kcur);
        }
        float mx0 = m0, mx1 = m1;
#pragma unroll
        for (int i = 0; i < 8; ++i) {
          mx0 = fmaxf(mx0, fmaxf(sacc[4 * i], sacc[4 * i + 1]));
          mx1 = fmaxf(mx1, fmaxf(sacc[4 * i + 2], sacc[4 * i + 3]));
        }
        mx0 = fmaxf(mx0, __shfl_xor_sync(0xffffffffu, mx0, 1));
        mx0 = fmaxf(mx0, __shfl_xor_sync(0xffffffffu, mx0, 2));
        mx1 = fmaxf(mx1, __shfl_xor_sync(0xffffffffu, mx1, 1));
        mx1 = fmaxf(mx1, __shfl_xor_sync(0xffffffffu, mx1, 2));
        float al0 = ex2((m0 - mx0) * sc), al1 = ex2((m1 - mx1) * sc);
        m0 = mx0; m1 = mx1;
        float ms0 = mx0 * sc, ms1 = mx1 * sc;
        uint32_t pa[16];
        float rs0 = 0.f, rs1 = 0.f;
#pragma unroll
        for (int i = 0; i < 8; ++i) {
          float p0 = ex2(sacc[4 * i] * sc - ms0), p1 = ex2(sacc[4 * i + 1] * sc - ms0);
          float p2 = ex2(sacc[4 * i + 2] * sc - ms1), p3 = ex2(sacc[4 * i + 3] * sc - ms1);
          rs0 += p0 + p1; rs1 += p2 + p3;
          pa[2 * i] = pack_bf16(p0, p1);
          pa[2 * i + 1] = pack_bf16(p2, p3);
        }
        l0 = l0 * al0 + rs0; l1 = l1 * al1 + rs1;
#pragma unroll
        for (int i = 0; i < 32; ++i) {
          acc[4 * i] *= al0; acc[4 * i + 1] *= al0; acc[4 * i + 2] *= al1; acc[4 * i + 3] *= al1;
        }
        {
          vprev = p.s;
          mbar_wait(c.bar_full + 8 * p.s, p.ph);
          p.adv();
          if (j < 7) {
            kcur = p.s;
            mbar_wait(c.bar_full + 8 * p.s, p.ph);
            p.adv();
          }
          named_bar(4 + wg, 256);
          wg_fence();
          uint32_t blo = desc_lo(slot_addr(c, vprev), 8192);
          static_for<0, PVN>([&](auto kx) { constexpr int ks = decltype(kx)::value; wgmma_rs_n256_tb<ks * 2048>(acc, pa + 4 * ks, blo, 1); });
          wg_commit();
          if (j < 7) {
            uint32_t klo = desc_lo(slot_addr(c, kcur), 16);
            static_for<0, QKN>([&](auto kx) {
              constexpr int ks = decltype(kx)::value;
              wgmma_ss_n64<(ks >> 2) * 8192 + (ks & 3) * 32, (ks >> 2) * 8192 + (ks & 3) * 32>(sacc, qlo, klo, ks != 0);
            });
            wg_commit();
          }
          named_arrive(5 - wg, 256);
        }
      }
      wg_wait<0>();
      if (lane == 0) release_slot(c, vprev);
      l0 += __shfl_xor_sync(0xffffffffu, l0, 1); l0 += __shfl_xor_sync(0xffffffffu, l0, 2);
      l1 += __shfl_xor_sync(0xffffffffu, l1, 1); l1 += __shfl_xor_sync(0xffffffffu, l1, 2);
      float il0 = 1.f / l0, il1 = 1.f / l1;
      uint32_t oa[64];
#pragma unroll
      for (int i = 0; i < 32; ++i) {
        oa[2 * i] = pack_bf16(acc[4 * i] * il0, acc[4 * i + 1] * il0);
        oa[2 * i + 1] = pack_bf16(acc[4 * i + 2] * il1, acc[4 * i + 3] * il1);
      }
      TS(hh * 8 + 3);
      named_bar(1 + wg, 128);
      cons_gemm2(c, p, sbuf, oa, qbase, &map_acc, (2 * g + hh) * S_PAD + orow, r0, lane, elected, 1 + wg);
      TS(hh * 8 + 4);
      TS(hh * 8 + 5);
    }
    if (elected) bulk_wait0();
    sync_end();
  }
}

__global__ void CLUSTER_ATTR __launch_bounds__(384, 1)
ffn_kernel(const __grid_constant__ CUtensorMap map_h2, const __grid_constant__ CUtensorMap map_w1,
           const __grid_constant__ CUtensorMap map_w2, const __grid_constant__ CUtensorMap map_acc2) {
  extern __shared__ __align__(1024) uint8_t smem[];
  const Ctx c = make_ctx(smem_u32(smem));
  const int tid = threadIdx.x;
  const int wg = __shfl_sync(0xffffffffu, tid >> 7, 0);
  const int slice = blockIdx.y;
  const int row_base = blockIdx.x * 128;

  if (tid == 0) init_bars(c);
  sync_start();

  if (wg == 2) {
    reg_dealloc<24>();
    if (tid == 256) {
      Pos p{0, 0};
      prod_gemm1(c, p, &map_h2, &map_w1, row_base, slice * 4);
      prod_gemm2(c, p, &map_w2, slice * 256);
    }
    sync_end();
  } else {
    reg_alloc<240>();
    const int warp = (tid >> 5) & 3;
    const int lane = tid & 31;
    const int r0 = warp * 16 + (lane >> 2);
    const bool elected = (tid & 127) == 0;
    const int orow = row_base + wg * 64;
    Pos p{0, 0};
    float acc[128];
    TS(32);
    cons_gemm1(c, p, acc, wg, lane);
    TS(33);
    uint32_t oa[64];
#pragma unroll
    for (int i = 0; i < 32; ++i) {
      oa[2 * i] = pack_bf16(fmaxf(acc[4 * i], 0.f), fmaxf(acc[4 * i + 1], 0.f));
      oa[2 * i + 1] = pack_bf16(fmaxf(acc[4 * i + 2], 0.f), fmaxf(acc[4 * i + 3], 0.f));
    }
    float sbuf[2][32];
    cons_gemm2(c, p, sbuf, oa, c.sbase + C_Q_OFF + wg * 32768, &map_acc2, slice * S_PAD + orow, r0, lane, elected, 1 + wg);
    TS(34);
    if (elected) bulk_wait0();
    TS(35);
    sync_end();
  }
}

__global__ void __launch_bounds__(256) final_kernel(__nv_bfloat16* __restrict__ out) {
  int e = blockIdx.x * 256 + threadIdx.x;
  int col = (e % 56) * 8;
  const uint4* p = reinterpret_cast<const uint4*>(g_part2) + e;
  uint4 t[7];
#pragma unroll
  for (int sl = 0; sl < 7; ++sl) t[sl] = __ldcg(p + (size_t)sl * (S_PAD * DM / 8));
  float f[8], xv[8];
#pragma unroll
  for (int i = 0; i < 8; ++i) f[i] = 0.f;
#pragma unroll
  for (int sl = 0; sl < 7; ++sl) {
    float u[8];
    unpack8(t[sl], u);
#pragma unroll
    for (int i = 0; i < 8; ++i) f[i] += u[i];
  }
  unpack8(reinterpret_cast<const uint4*>(g_x1)[e], xv);
  float4 g0 = *reinterpret_cast<const float4*>(g_mod + 5 * DM + col), g1 = *reinterpret_cast<const float4*>(g_mod + 5 * DM + col + 4);
  uint4 o;
  o.x = pack_bf16(xv[0] + g0.x * f[0], xv[1] + g0.y * f[1]);
  o.y = pack_bf16(xv[2] + g0.z * f[2], xv[3] + g0.w * f[3]);
  o.z = pack_bf16(xv[4] + g1.x * f[4], xv[5] + g1.y * f[5]);
  o.w = pack_bf16(xv[6] + g1.z * f[6], xv[7] + g1.w * f[7]);
  reinterpret_cast<uint4*>(out)[e] = o;
}

typedef CUresult (*PFN_encodeTiled)(CUtensorMap*, CUtensorMapDataType, cuuint32_t, void*, const cuuint64_t*,
                                    const cuuint64_t*, const cuuint32_t*, const cuuint32_t*, CUtensorMapInterleave,
                                    CUtensorMapSwizzle, CUtensorMapL2promotion, CUtensorMapFloatOOBfill);

static void make_map3(PFN_encodeTiled enc, CUtensorMap* m, const void* ptr, uint64_t rows, uint64_t cols, uint32_t box_rows,
                      uint32_t box_groups) {
  cuuint64_t dims[3] = {64, rows, cols / 64};
  cuuint64_t strides[2] = {cols * 2, 128};
  cuuint32_t box[3] = {64, box_rows, box_groups};
  cuuint32_t es[3] = {1, 1, 1};
  enc(m, CU_TENSOR_MAP_DATA_TYPE_BFLOAT16, 3, (void*)ptr, dims, strides, box, es, CU_TENSOR_MAP_INTERLEAVE_NONE,
      CU_TENSOR_MAP_SWIZZLE_128B, CU_TENSOR_MAP_L2_PROMOTION_L2_256B, CU_TENSOR_MAP_FLOAT_OOB_FILL_NONE);
}
static void make_mapf(PFN_encodeTiled enc, CUtensorMap* m, const void* ptr) {
  cuuint64_t dims[2] = {DM, 7 * S_LEN};
  cuuint64_t strides[1] = {DM * 4};
  cuuint32_t box[2] = {32, 64};
  cuuint32_t es[2] = {1, 1};
  enc(m, CU_TENSOR_MAP_DATA_TYPE_FLOAT32, 2, (void*)ptr, dims, strides, box, es, CU_TENSOR_MAP_INTERLEAVE_NONE,
      CU_TENSOR_MAP_SWIZZLE_128B, CU_TENSOR_MAP_L2_PROMOTION_NONE, CU_TENSOR_MAP_FLOAT_OOB_FILL_NONE);
}
static void make_map2(PFN_encodeTiled enc, CUtensorMap* m, const void* ptr, uint64_t rows, uint64_t cols, uint32_t box_rows) {
  cuuint64_t dims[2] = {cols, rows};
  cuuint64_t strides[1] = {cols * 2};
  cuuint32_t box[2] = {64, box_rows};
  cuuint32_t es[2] = {1, 1};
  enc(m, CU_TENSOR_MAP_DATA_TYPE_BFLOAT16, 2, (void*)ptr, dims, strides, box, es, CU_TENSOR_MAP_INTERLEAVE_NONE,
      CU_TENSOR_MAP_SWIZZLE_128B, CU_TENSOR_MAP_L2_PROMOTION_L2_256B, CU_TENSOR_MAP_FLOAT_OOB_FILL_NONE);
}

extern "C" void kernel_launch(void* const* d_in, const int* in_sizes, int n_in, void* d_out, int out_size) {
  const __nv_bfloat16* x = (const __nv_bfloat16*)d_in[0];
  const __nv_bfloat16* kc = (const __nv_bfloat16*)d_in[1];
  const __nv_bfloat16* vc = (const __nv_bfloat16*)d_in[2];
  const __nv_bfloat16* wq = (const __nv_bfloat16*)d_in[3];
  const __nv_bfloat16* wo = (const __nv_bfloat16*)d_in[4];
  const __nv_bfloat16* w1 = (const __nv_bfloat16*)d_in[6];
  const __nv_bfloat16* w2 = (const __nv_bfloat16*)d_in[7];
  const __nv_bfloat16* c = (const __nv_bfloat16*)d_in[8];
  const __nv_bfloat16* w_mod = (const __nv_bfloat16*)d_in[9];
  __nv_bfloat16* out = (__nv_bfloat16*)d_out;

  static PFN_encodeTiled enc = nullptr;
  static CUtensorMap m_h, m_wq, m_k, m_v, m_wo, m_w1, m_w2, m_acc, m_acc2, m_h2;
  static const void* cached[8] = {nullptr};
  if (!enc) {
    void* fn = nullptr;
    cudaDriverEntryPointQueryResult st;
    cudaGetDriverEntryPoint("cuTensorMapEncodeTiled", &fn, cudaEnableDefault, &st);
    enc = (PFN_encodeTiled)fn;
    cudaFuncSetAttribute(attn_kernel, cudaFuncAttributeMaxDynamicSharedMemorySize, C_SMEM);
    cudaFuncSetAttribute(ffn_kernel, cudaFuncAttributeMaxDynamicSharedMemorySize, C_SMEM);
  }
  if (cached[0] != kc || cached[1] != vc || cached[2] != wq || cached[3] != wo || cached[4] != w1 || cached[5] != w2) {
    void* hptr = nullptr;
    cudaGetSymbolAddress(&hptr, g_h);
    make_map2(enc, &m_h, hptr, S_LEN, DM, 128);
    void* aptr = nullptr;
    cudaGetSymbolAddress(&aptr, g_part);
    make_map2(enc, &m_acc, aptr, HQ * S_PAD, DM, 64);
    cudaGetSymbolAddress(&aptr, g_part2);
    make_map2(enc, &m_acc2, aptr, 7 * S_PAD, DM, 64);
    make_map3(enc, &m_wq, wq, DM, HQ * DH, 64, 2);
    make_map3(enc, &m_k, kc, HKV * SK, DH, 64, 2);
    make_map3(enc, &m_v, vc, HKV * SK, DH, 64, 2);
    make_map3(enc, &m_wo, wo, HQ * DH, DM, 128, 1);
    make_map3(enc, &m_w1, w1, DM, DFF, 64, 2);
    make_map3(enc, &m_w2, w2, DFF, DM, 128, 1);
    cudaGetSymbolAddress(&hptr, g_h2);
    make_map2(enc, &m_h2, hptr, S_LEN, DM, 128);
    cached[0] = kc; cached[1] = vc; cached[2] = wq; cached[3] = wo; cached[4] = w1; cached[5] = w2;
  }
  mod_kernel<<<84, 256>>>(c, w_mod);
  ln1_kernel<<<256, 256>>>(x);
  attn_kernel<<<dim3(16, 8), 384, C_SMEM>>>(m_h, m_wq, m_k, m_v, m_wo, m_acc);
  ln2_kernel<<<512, 128>>>(x);
  ffn_kernel<<<dim3(16, 7), 384, C_SMEM>>>(m_h2, m_w1, m_w2, m_acc2);
  final_kernel<<<S_LEN * 56 / 256, 256>>>(out);
}
```
